```python
import torch

def _softmax(x, axis=-1):
    return torch.softmax(x, dim=axis)
def _gelu(x):
    return torch.nn.functional.gelu(x, approximate="tanh")
def _silu(x):
    return torch.nn.functional.silu(x)
def _sigmoid(x):
    return torch.sigmoid(x)
def _layernorm(x, axis=-1, eps=1e-5):
    m = x.mean(dim=axis, keepdim=True)
    v = x.var(dim=axis, keepdim=True, unbiased=False)
    return (x - m) / torch.sqrt(v + eps)
def _scatter_add(tgt, idx, src, axis=0):
    return tgt.clone().index_add_(axis, idx, src)
def _segment_sum(src, seg, n):
    out = torch.zeros((n,) + src.shape[1:], dtype=src.dtype)
    return out.index_add_(0, seg, src)
def _pad(x, pw):
    flat = tuple(v for pair in reversed(pw) for v in pair)
    return torch.nn.functional.pad(x, flat)

kernel_name = 'concat_heads__grouped_kv_mqa__ssm_conv_s4d__prompt'

def setup_inputs():

    _w = (lambda a: (lambda t: t.to(torch.bfloat16) if t.is_floating_point() else t)(torch.as_tensor(a)))
    def _A_setup():
        B, S, D, H = 1, 2048, 448, 16
        Dh = D // H
        return {
            "x": _w((lambda *s: torch.randn(*s, dtype=torch.bfloat16) * 0.05)(B, S, D)),
            "wq": _w((lambda *s: torch.randn(*s, dtype=torch.bfloat16) * 1.6)(D, H * Dh)),
            "wk": _w((lambda *s: torch.randn(*s, dtype=torch.bfloat16) * 1.6)(D, Dh)),
            "wv": _w((lambda *s: torch.randn(*s, dtype=torch.bfloat16) * 0.05)(D, Dh)),
            "wo": _w((lambda *s: torch.randn(*s, dtype=torch.bfloat16) * 0.05)(H * Dh, D)),
        }
    _A_in = _A_setup()

    def _B_setup():
        Bsz, L, D, N = 1, 2048, 448, 256
        return {
            "u": _w((lambda *s: torch.randn(*s, dtype=torch.bfloat16) * 0.05)(Bsz, L, D)),
            "log_A_real": _w((lambda *s: torch.randn(*s, dtype=torch.bfloat16) * 3.2)(D, N) * 0.5),
            "A_imag": _w((lambda *s: torch.randn(*s, dtype=torch.bfloat16) * 0.05)(D, N) * 3.14),
            "C_real": _w((lambda *s: torch.randn(*s, dtype=torch.bfloat16) * 0.8)(D, N) / N ** 0.5),
            "C_imag": _w((lambda *s: torch.randn(*s, dtype=torch.bfloat16) * 0.8)(D, N) / N ** 0.5),
            "log_dt": _w((lambda *s: torch.randn(*s, dtype=torch.bfloat16) * 0.05)(D) * 0.5 - 4.0),
            "D_skip": _w((lambda *s: torch.randn(*s, dtype=torch.bfloat16) * 0.1)(D)),
        }
    _B_in = _B_setup()

    return {
        "A_x": _A_in["x"],
        "A_wq": _A_in["wq"],
        "A_wk": _A_in["wk"],
        "A_wv": _A_in["wv"],
        "A_wo": _A_in["wo"],
        "B_u": _B_in["u"],
        "B_log_A_real": _B_in["log_A_real"],
        "B_A_imag": _B_in["A_imag"],
        "B_C_real": _B_in["C_real"],
        "B_C_imag": _B_in["C_imag"],
        "B_log_dt": _B_in["log_dt"],
        "B_D_skip": _B_in["D_skip"],
    }

def reference(A_x, A_wq, A_wk, A_wv, A_wo, B_u, B_log_A_real, B_A_imag, B_C_real, B_C_imag, B_log_dt, B_D_skip):
    def _A_ref(x, wq, wk, wv, wo):
        B, S, D = x.shape
        H = 16
        Dh = D // H
        q = (lambda x, *d: x.permute(*d))((x @ wq).reshape(B, S, H, Dh), 0, 2, 1, 3)
        k = x @ wk
        v = x @ wv
        scores = torch.einsum("bhqd,bkd->bhqk", q, k) * (Dh ** -0.5)
        p = _softmax(scores, axis=-1)
        o = torch.einsum("bhqk,bkd->bhqd", p, v)
        return (lambda x, *d: x.permute(*d))(o, 0, 2, 1, 3).reshape(B, S, H * Dh) @ wo

    def _B_ref(u, log_A_real, A_imag, C_real, C_imag, log_dt, D_skip):
        L = u.shape[1]
        dt = torch.exp(log_dt)
        A = -torch.exp(log_A_real) + 1j * A_imag
        C = (C_real + 1j * C_imag) * dt[:, None]
        pos = (lambda x, dt: x.to(dt))(torch.arange(L), log_dt.dtype)
        P = torch.exp((A * dt[:, None])[:, :, None] * pos[None, None, :])
        K = 2.0 * torch.einsum("dn,dnl->dl", C, P).real
        L2 = 2 * L
        u_t = (lambda x, *d: x.permute(*d))(u, 0, 2, 1)
        Kf = (lambda x, *a, **k: torch.fft.rfft(x.float(), *a, **k))(K, L2)
        Uf = (lambda x, *a, **k: torch.fft.rfft(x.float(), *a, **k))(u_t, L2)
        y = (lambda x, *a, **k: torch.fft.irfft(x, *a, **k).to(torch.bfloat16))(Uf * Kf[None, :, :], L2)[:, :, :L]
        y = (lambda x, *d: x.permute(*d))(y, 0, 2, 1)
        return y + u * D_skip[None, None, :]

    a = _A_ref(A_x, A_wq, A_wk, A_wv, A_wo)
    b = _B_ref(B_u, B_log_A_real, B_A_imag, B_C_real, B_C_imag, B_log_dt, B_D_skip)
    return torch.concatenate([a, b], axis=-1)
```

```cpp
#include <cuda_runtime.h>
#include <cuda.h>
#include <cuda_bf16.h>
#include <cuda_fp16.h>
#include <stdint.h>

template<int TB> __device__ __forceinline__ void wg_bf16_n32_rs(float* d, uint32_t a0, uint32_t a1, uint32_t a2, uint32_t a3, uint64_t db, int sd) {
  asm volatile("{\n.reg .pred p;\nsetp.ne.b32 p, %21, 0;\nwgmma.mma_async.sync.aligned.m64n32k16.f32.bf16.bf16 {%0,%1,%2,%3,%4,%5,%6,%7,%8,%9,%10,%11,%12,%13,%14,%15}, {%16,%17,%18,%19}, %20, p, 1, 1, %22;\n}\n"
   : "+f"(d[0]),"+f"(d[1]),"+f"(d[2]),"+f"(d[3]),"+f"(d[4]),"+f"(d[5]),"+f"(d[6]),"+f"(d[7]),"+f"(d[8]),"+f"(d[9]),"+f"(d[10]),"+f"(d[11]),"+f"(d[12]),"+f"(d[13]),"+f"(d[14]),"+f"(d[15]) : "r"(a0), "r"(a1), "r"(a2), "r"(a3), "l"(db), "r"(sd), "n"(TB));
}
template<int TB> __device__ __forceinline__ void wg_bf16_n64_rs(float* d, uint32_t a0, uint32_t a1, uint32_t a2, uint32_t a3, uint64_t db, int sd) {
  asm volatile("{\n.reg .pred p;\nsetp.ne.b32 p, %37, 0;\nwgmma.mma_async.sync.aligned.m64n64k16.f32.bf16.bf16 {%0,%1,%2,%3,%4,%5,%6,%7,%8,%9,%10,%11,%12,%13,%14,%15,%16,%17,%18,%19,%20,%21,%22,%23,%24,%25,%26,%27,%28,%29,%30,%31}, {%32,%33,%34,%35}, %36, p, 1, 1, %38;\n}\n"
   : "+f"(d[0]),"+f"(d[1]),"+f"(d[2]),"+f"(d[3]),"+f"(d[4]),"+f"(d[5]),"+f"(d[6]),"+f"(d[7]),"+f"(d[8]),"+f"(d[9]),"+f"(d[10]),"+f"(d[11]),"+f"(d[12]),"+f"(d[13]),"+f"(d[14]),"+f"(d[15]),"+f"(d[16]),"+f"(d[17]),"+f"(d[18]),"+f"(d[19]),"+f"(d[20]),"+f"(d[21]),"+f"(d[22]),"+f"(d[23]),"+f"(d[24]),"+f"(d[25]),"+f"(d[26]),"+f"(d[27]),"+f"(d[28]),"+f"(d[29]),"+f"(d[30]),"+f"(d[31]) : "r"(a0), "r"(a1), "r"(a2), "r"(a3), "l"(db), "r"(sd), "n"(TB));
}
template<int TA, int TB> __device__ __forceinline__ void wg_bf16_n8_ss(float* d, uint64_t da, uint64_t db, int sd) {
  asm volatile("{\n.reg .pred p;\nsetp.ne.b32 p, %6, 0;\nwgmma.mma_async.sync.aligned.m64n8k16.f32.bf16.bf16 {%0,%1,%2,%3}, %4, %5, p, 1, 1, %7, %8;\n}\n"
   : "+f"(d[0]),"+f"(d[1]),"+f"(d[2]),"+f"(d[3]) : "l"(da), "l"(db), "r"(sd), "n"(TA), "n"(TB));
}
template<int TA, int TB> __device__ __forceinline__ void wg_bf16_n56_ss(float* d, uint64_t da, uint64_t db, int sd) {
  asm volatile("{\n.reg .pred p;\nsetp.ne.b32 p, %30, 0;\nwgmma.mma_async.sync.aligned.m64n56k16.f32.bf16.bf16 {%0,%1,%2,%3,%4,%5,%6,%7,%8,%9,%10,%11,%12,%13,%14,%15,%16,%17,%18,%19,%20,%21,%22,%23,%24,%25,%26,%27}, %28, %29, p, 1, 1, %31, %32;\n}\n"
   : "+f"(d[0]),"+f"(d[1]),"+f"(d[2]),"+f"(d[3]),"+f"(d[4]),"+f"(d[5]),"+f"(d[6]),"+f"(d[7]),"+f"(d[8]),"+f"(d[9]),"+f"(d[10]),"+f"(d[11]),"+f"(d[12]),"+f"(d[13]),"+f"(d[14]),"+f"(d[15]),"+f"(d[16]),"+f"(d[17]),"+f"(d[18]),"+f"(d[19]),"+f"(d[20]),"+f"(d[21]),"+f"(d[22]),"+f"(d[23]),"+f"(d[24]),"+f"(d[25]),"+f"(d[26]),"+f"(d[27]) : "l"(da), "l"(db), "r"(sd), "n"(TA), "n"(TB));
}


#define WG_FENCE asm volatile("wgmma.fence.sync.aligned;" ::: "memory")
#define WG_COMMIT asm volatile("wgmma.commit_group.sync.aligned;" ::: "memory")
#define WG_WAIT(n) asm volatile("wgmma.wait_group.sync.aligned %0;" :: "n"(n) : "memory")
#define PROXY_FENCE asm volatile("fence.proxy.async.shared::cta;" ::: "memory")

constexpr int GM0 = 1, GM3 = 2, GM1 = 3, FORCE = 6;
typedef __nv_bfloat16 bf16;
constexpr int S_ = 2048, NM = 256;

__device__ __forceinline__ uint64_t mkdesc(uint32_t addr, uint32_t lbo, uint32_t sbo, uint32_t mode) {
    return (uint64_t)((addr & 0x3FFFF) >> 4) | ((uint64_t)(lbo >> 4) << 16) | ((uint64_t)(sbo >> 4) << 32) | ((uint64_t)mode << 62);
}
__device__ __forceinline__ uint32_t smem_u32(const void* p) { return (uint32_t)__cvta_generic_to_shared(p); }
__device__ __forceinline__ void mbar_init(uint32_t bar, uint32_t cnt) { asm volatile("mbarrier.init.shared::cta.b64 [%0], %1;" :: "r"(bar), "r"(cnt)); }
__device__ __forceinline__ void mbar_expect_tx(uint32_t bar, uint32_t bytes) { asm volatile("mbarrier.arrive.expect_tx.shared::cta.b64 _, [%0], %1;" :: "r"(bar), "r"(bytes) : "memory"); }
__device__ __forceinline__ void mbar_arrive(uint32_t bar) { asm volatile("mbarrier.arrive.shared::cta.b64 _, [%0];" :: "r"(bar) : "memory"); }
__device__ __forceinline__ void mbar_wait(uint32_t bar, uint32_t parity) {
    asm volatile("{\n.reg .pred p;\n.reg .u32 n;\nmov.u32 n, 0;\nLAB_WAIT%=:\nmbarrier.try_wait.parity.shared::cta.b64 p, [%0], %1;\n@p bra DONE%=;\n"
                 "add.u32 n, n, 1;\nsetp.lt.u32 p, n, 4000000;\n@p bra LAB_WAIT%=;\ntrap;\nDONE%=:\n}" :: "r"(bar), "r"(parity) : "memory");
}
__device__ __forceinline__ bool mbar_test(uint32_t bar, uint32_t parity) {
    uint32_t ok;
    asm volatile("{\n.reg .pred p;\nmbarrier.test_wait.parity.shared::cta.b64 p, [%1], %2;\nselp.u32 %0, 1, 0, p;\n}" : "=r"(ok) : "r"(bar), "r"(parity) : "memory");
    return ok != 0;
}
__device__ __forceinline__ void bulk_g2s(uint32_t dst, const void* src, uint32_t bytes, uint32_t bar) {
    asm volatile("cp.async.bulk.shared::cluster.global.mbarrier::complete_tx::bytes [%0], [%1], %2, [%3];" :: "r"(dst), "l"(src), "r"(bytes), "r"(bar) : "memory");
}
__device__ __forceinline__ void bar_sync(int id, int n) { asm volatile("bar.sync %0, %1;" :: "r"(id), "r"(n) : "memory"); }
template<int N> __device__ __forceinline__ void fence_f(float* x) {
    #pragma unroll
    for (int i = 0; i < N; i++) asm volatile("" : "+f"(x[i]) :: "memory");
}
template<int N> __device__ __forceinline__ void fence_r(uint32_t* x) {
    #pragma unroll
    for (int i = 0; i < N; i++) asm volatile("" : "+r"(x[i]) :: "memory");
}
__device__ __forceinline__ uint32_t pack_bf16(float lo, float hi) { uint32_t r; asm("cvt.rn.bf16x2.f32 %0, %1, %2;" : "=r"(r) : "f"(hi), "f"(lo)); return r; }
__device__ __forceinline__ uint32_t pack_f16(float lo, float hi) { uint32_t r; asm("cvt.rn.f16x2.f32 %0, %1, %2;" : "=r"(r) : "f"(hi), "f"(lo)); return r; }
__device__ __forceinline__ float bf_lo(uint32_t v) { return __uint_as_float(v << 16); }
__device__ __forceinline__ float bf_hi(uint32_t v) { return __uint_as_float(v & 0xFFFF0000u); }
__device__ __forceinline__ float ex2f(float x) { float r; asm("ex2.approx.ftz.f32 %0, %1;" : "=f"(r) : "f"(x)); return r; }
__device__ __forceinline__ void sts32(uint32_t a, uint32_t v) { asm volatile("st.shared.b32 [%0], %1;" :: "r"(a), "r"(v) : "memory"); }
__device__ __forceinline__ uint32_t lds32(uint32_t a) { uint32_t v; asm volatile("ld.shared.b32 %0, [%1];" : "=r"(v) : "r"(a) : "memory"); return v; }


__device__ __forceinline__ void tma2d(uint32_t dst, const CUtensorMap* m, int c0, int c1, uint32_t bar) {
    asm volatile("cp.async.bulk.tensor.2d.shared::cluster.global.mbarrier::complete_tx::bytes [%0], [%1, {%3, %4}], [%2];" :: "r"(dst), "l"(m), "r"(bar), "r"(c0), "r"(c1) : "memory");
}
__device__ __forceinline__ void sts128(uint32_t a, uint4 v) { asm volatile("st.shared.v4.b32 [%0], {%1,%2,%3,%4};" :: "r"(a), "r"(v.x), "r"(v.y), "r"(v.z), "r"(v.w) : "memory"); }
__device__ __forceinline__ void sts64f(uint32_t a, float x, float y) { asm volatile("st.shared.v2.f32 [%0], {%1,%2};" :: "r"(a), "f"(x), "f"(y) : "memory"); }
__device__ __forceinline__ float lds32f(uint32_t a) { float v; asm volatile("ld.shared.f32 %0, [%1];" : "=f"(v) : "r"(a) : "memory"); return v; }
__device__ __forceinline__ unsigned ld_acquire(const unsigned* p) { unsigned v; asm volatile("ld.acquire.gpu.global.u32 %0, [%1];" : "=r"(v) : "l"(p) : "memory"); return v; }
__device__ __forceinline__ void spin_until(const unsigned* p, unsigned target) {
    #pragma unroll 1
    for (int i = 0; i < (1 << 22); i++) { if (ld_acquire(p) >= target) return; __nanosleep(200); }
    __trap();
}

__device__ __forceinline__ void ldsm4t(uint32_t* r, uint32_t a) {
    asm volatile("ldmatrix.sync.aligned.m8n8.x4.trans.shared.b16 {%0,%1,%2,%3}, [%4];" : "=r"(r[0]), "=r"(r[1]), "=r"(r[2]), "=r"(r[3]) : "r"(a) : "memory");
}
__device__ __forceinline__ void mma_f16(float* c, const uint32_t* a, uint32_t b0, uint32_t b1) {
    asm volatile("mma.sync.aligned.m16n8k16.row.col.f32.f16.f16.f32 {%0,%1,%2,%3}, {%4,%5,%6,%7}, {%8,%9}, {%0,%1,%2,%3};"
        : "+f"(c[0]), "+f"(c[1]), "+f"(c[2]), "+f"(c[3]) : "r"(a[0]), "r"(a[1]), "r"(a[2]), "r"(a[3]), "r"(b0), "r"(b1));
}
__device__ __forceinline__ uint4 lds128(uint32_t a) { uint4 v; asm volatile("ld.shared.v4.b32 {%0,%1,%2,%3}, [%4];" : "=r"(v.x), "=r"(v.y), "=r"(v.z), "=r"(v.w) : "r"(a) : "memory"); return v; }
__device__ __forceinline__ void warp_arrive(uint32_t bar, int lane) { __syncwarp(); if (lane == 0) mbar_arrive(bar); }
__device__ __forceinline__ void bulk_s2g(void* dst, uint32_t src, uint32_t bytes) {
    asm volatile("cp.async.bulk.global.shared::cta.bulk_group [%0], [%1], %2;" :: "l"(dst), "r"(src), "r"(bytes) : "memory");
}
__device__ __forceinline__ void tma2d_store(const CUtensorMap* m, int c0, int c1, uint32_t src) {
    asm volatile("cp.async.bulk.tensor.2d.global.shared::cta.bulk_group [%0, {%2, %3}], [%1];\n cp.async.bulk.commit_group;\n cp.async.bulk.wait_group.read 0;"
                 :: "l"(m), "r"(src), "r"(c0), "r"(c1) : "memory");
}
__device__ __forceinline__ void bulk_publish(unsigned* flag) {
    asm volatile("cp.async.bulk.commit_group;\n cp.async.bulk.wait_group 0;\n fence.proxy.async.global;\n red.release.gpu.global.add.u32 [%0], 1;" :: "l"(flag) : "memory");
}

__device__ __align__(1024) uint8_t g_KV[32 * 8192];
__device__ __align__(1024) uint8_t g_O[32 * 8 * 8192];
__device__ __align__(1024) uint8_t g_KP[64 * 9216];
__device__ __align__(1024) bf16 g_UT[448 * S_];
__device__ __align__(1024) bf16 g_YT[448 * S_];
__device__ __align__(128) unsigned g_cnt[2 * 64 * 32];
__device__ unsigned g_ticket;
#define CNT(i) (cnt + (i) * 32)

constexpr float QSCALE = 0.18898223650461362f * 1.4426950408889634f;
struct Params { const bf16 *wk, *wv, *lar, *aim, *cre, *cim, *ldt, *dsk; };

constexpr int SM_W = 114688;
constexpr int SM_Z = 131072, SM_KP1 = SM_Z, SM_U0 = SM_Z + 18432;
constexpr int SM_SC0 = 172032, SM_OSV = SM_SC0;
constexpr int SM_KP0 = 204800, SM_KVW = SM_KP0, SM_QS = 214016, SM_BAR = 230400, SM_TOTAL = SM_BAR + 512;
constexpr int SM_WO0 = SM_Z, SM_WO1 = 0, SM_OT = 65536, SM_YT = 196608, SM_YS = SM_QS;
constexpr int SM_KP3 = SM_KP0;
constexpr int SB_T = 4096;
constexpr int B_XF = 0, B_WQF = 56, B_UF = 64, B_KVW = 72, B_PD = 80, B_QR = 88, B_UL = 96, B_WF = 104, B_KG = 112, B_BD = 144,
              B_KVF = 176, B_KVE = 208, B_OF = 240, B_GMAX = 320, B_YF = 304, B_QF = 312, B_PAR = 352, B_KS = 360, B_PB = 368, B_UT = 376, B_OP = 448, B_CMAX = 384;

struct cf { float r, i; };
__device__ __forceinline__ cf csq(cf a) { cf o; o.r = fmaf(a.r, a.r, -a.i * a.i); o.i = 2.f * a.r * a.i; return o; }
__device__ __forceinline__ cf cexp_p(float a2, float ai, float p) {
    float mag = ex2f(a2 * p);
    float x = ai * p;
    float k = rintf(x * 0.15915494309189535f);
    float rr = fmaf(x, 0.15915494309189535f, -k);
    rr = fmaf(x, 6.420638e-09f, rr);
    rr *= 6.283185307179586f;
    cf o; o.r = mag * __cosf(rr); o.i = mag * __sinf(rr); return o;
}
struct p2 { __half2 r, i; };
__device__ __forceinline__ __half2 u2h(uint32_t u) { return *(__half2*)&u; }
__device__ __forceinline__ uint32_t h2u(__half2 h) { return *(uint32_t*)&h; }
__device__ __forceinline__ __half2 mk_mul(cf e) { return u2h(pack_f16(e.r, e.i)); }
__device__ __forceinline__ p2 pmul(p2 x, __half2 e) {
    p2 y; __half2 er = __low2half2(e), ei = __high2half2(e);
    y.r = __hfma2(__hneg2(x.i), ei, __hmul2(x.r, er));
    y.i = __hfma2(x.r, ei, __hmul2(x.i, er));
    return y;
}
__device__ __forceinline__ void st_chunk(uint32_t a, const p2& x0, const p2& x1, const p2& x2, const p2& x3) {
    sts128(a, make_uint4(h2u(x0.r), h2u(x1.r), h2u(x2.r), h2u(x3.r)));
    sts128(a + 4096, make_uint4(h2u(x0.i), h2u(x1.i), h2u(x2.i), h2u(x3.i)));
}
__device__ __forceinline__ void conv_loadA(uint32_t* a, uint32_t addr) {
    #pragma unroll
    for (int ii = 0; ii < 2; ii++) {
        a[4*ii+0] = lds32(addr + ii * 64);
        a[4*ii+1] = lds32(addr + ii * 64 + 256);
        a[4*ii+2] = lds32(addr + ii * 64 + 16);
        a[4*ii+3] = lds32(addr + ii * 64 + 272);
    }
}
template<int NCG> __device__ __forceinline__ void conv_half(float* acc, uint32_t* a, uint32_t* an, uint32_t addr_next, uint64_t db) {
    fence_r<8>(a);
    WG_FENCE;
    #pragma unroll
    for (int ii = 0; ii < 2; ii++)
        #pragma unroll
        for (int cg = 0; cg < NCG; cg++)
            wg_bf16_n32_rs<0>(acc + 16 * cg, a[4*ii], a[4*ii+1], a[4*ii+2], a[4*ii+3], db + 2 * ii + 32 * cg, 1);
    WG_COMMIT;
    conv_loadA(an, addr_next);
    WG_WAIT(0);
    fence_f<16 * NCG>(acc);
}
template<int NCG> __device__ __forceinline__ void conv_steps(float* acc, uint32_t* aA, uint32_t* aB, uint32_t& addr, uint64_t& db) {
    #pragma unroll 1
    for (int it = 0; it < 2; it++) {
        conv_half<NCG>(acc, aA, aB, addr + 128, db);
        conv_half<NCG>(acc, aB, aA, addr + 512, db + 4);
        addr += 512; db += 16;
    }
}

struct s4d_in { uint32_t lar, aim, cre, cim, ldt; };
__device__ __forceinline__ s4d_in s4d_load(const Params& p, int d, int tw) {
    s4d_in in;
    const size_t idx = (size_t)d * (NM / 2) + tw;
    in.ldt = __ldg((const unsigned short*)p.ldt + d);
    in.cre = __ldg((const uint32_t*)p.cre + idx); in.cim = __ldg((const uint32_t*)p.cim + idx);
    in.lar = __ldg((const uint32_t*)p.lar + idx); in.aim = __ldg((const uint32_t*)p.aim + idx);
    return in;
}
__device__ __forceinline__ uint32_t mix(uint32_t a, uint32_t b) { return __byte_perm(a, b, 0x7610); }
struct mode_t_ { __half2 m1, m2, m4, m8, m16, m32, m256, m512, m1024; p2 f0; float cr, ci, xr, xi; };
__device__ __forceinline__ mode_t_ s4d_prep(float lar, float aim, float cr, float ci, float dt, float& klast) {
    float ar = __bfloat162float(__float2bfloat16(expf(lar)));
    float a2 = -(ar * dt) * 1.4426950408889634f, ai = aim * dt;
    cf e1 = cexp_p(a2, ai, 1.f), e16 = cexp_p(a2, ai, 16.f), e256 = cexp_p(a2, ai, 256.f);
    cf e2 = csq(e1), e4 = csq(e2), e8 = csq(e4);
    cf e32 = csq(e16), e64 = csq(e32), e128 = csq(e64);
    cf e512 = csq(e256), e1024 = csq(e512), e2048 = csq(e1024);
    klast += cr * e2048.r - ci * e2048.i;
    mode_t_ m;
    e8.i = -e8.i; e16.i = -e16.i; e32.i = -e32.i;
    m.m1 = mk_mul(e1); m.m2 = mk_mul(e2); m.m4 = mk_mul(e4); m.m8 = mk_mul(e8); m.m16 = mk_mul(e16); m.m32 = mk_mul(e32);
    m.m256 = mk_mul(e256); m.m512 = mk_mul(e512); m.m1024 = mk_mul(e1024);
    m.f0.r = u2h(pack_f16(1.f, e64.r)); m.f0.i = u2h(pack_f16(0.f, -e64.i));
    m.cr = cr; m.ci = ci; m.xr = cr * e128.r - ci * e128.i; m.xi = cr * e128.i + ci * e128.r;
    return m;
}

template<class F> __device__ __forceinline__ void s4d_kgen(const s4d_in& in, uint32_t sb, uint32_t sKP, uint32_t scm, F&& before_scratch, uint32_t gate2, int wg, int warp, int tid) {
    const int tw = tid & 127, lane = tid & 31, g = lane >> 2, t = lane & 3;
    const float dt = __bfloat162float(__float2bfloat16(expf(bf_lo(in.ldt))));
    {
        uint32_t m = __vmaxu2(in.cre & 0x7FFF7FFFu, in.cim & 0x7FFF7FFFu);
        m = __reduce_max_sync(0xffffffffu, max(m & 0xFFFFu, m >> 16));
        if (lane == 0) sts32(scm + 4 * warp, m);
    }
    float klast = 0.f;
    mode_t_ md = s4d_prep(bf_lo(in.lar), bf_lo(in.aim), bf_lo(in.cre), bf_lo(in.cim), dt, klast);
    const mode_t_ md2 = s4d_prep(bf_hi(in.lar), bf_hi(in.aim), bf_hi(in.cre), bf_hi(in.cim), dt, klast);
    bar_sync(1 + wg, 128);
    float cscale, kscale;
    {
        uint4 mm = lds128(scm);
        int e = (int)(max(max(mm.x, mm.y), max(mm.z, mm.w)) >> 7);
        e = min(max(e, 1), 253);
        cscale = __uint_as_float((uint32_t)(254 - e) << 23);
        kscale = __uint_as_float((uint32_t)e << 23) * (2.f * dt);
    }
    #pragma unroll
    for (int o = 16; o > 0; o >>= 1) klast += __shfl_xor_sync(0xffffffffu, klast, o);
    before_scratch();
    float kd[20];
    #pragma unroll
    for (int i = 0; i < 20; i++) kd[i] = 0.f;
    const uint32_t sA = sb + warp * 8192;
    const uint32_t x7 = (lane & 7) << 4, wrow = sA + lane * 128;
    const uint32_t la = sA + ((lane & 7) + 8 * (lane >> 4)) * 128 + (((5 + ((lane >> 3) & 1)) << 4) ^ x7);
    const uint32_t lbr = sA + (lane & 15) * 128, lb0 = lbr + (((lane >> 4) << 4) ^ x7), lb1 = lbr + (((2 + (lane >> 4)) << 4) ^ x7), lb2 = lbr + (64 ^ x7);
    #pragma unroll 1
    for (int pass = 0; pass < 2; pass++) {
        {
            const p2 f0 = md.f0, f1 = pmul(f0, md.m8), f2 = pmul(f0, md.m16), f3 = pmul(f1, md.m16);
            st_chunk(wrow + (80 ^ x7), f0, f1, f2, f3);
            st_chunk(wrow + (96 ^ x7), pmul(f0, md.m32), pmul(f1, md.m32), pmul(f2, md.m32), pmul(f3, md.m32));
        }
        {
            p2 g0, g1, g2, g3, g4, g6;
            g0.r = u2h(pack_f16(md.cr * cscale, md.xr * cscale)); g0.i = u2h(pack_f16(md.ci * cscale, md.xi * cscale));
            g1 = pmul(g0, md.m1); g2 = pmul(g0, md.m2); g3 = pmul(g1, md.m2);
            st_chunk(wrow + (0 ^ x7), g0, g1, g2, g3);
            g4 = pmul(g0, md.m4); g6 = pmul(g2, md.m4);
            st_chunk(wrow + (16 ^ x7), g4, pmul(g1, md.m4), g6, pmul(g3, md.m4));
            p2 h0 = pmul(g0, md.m256), h4 = pmul(g4, md.m256);
            st_chunk(wrow + (32 ^ x7), h0, pmul(g2, md.m256), h4, pmul(g6, md.m256));
            p2 i0 = pmul(g0, md.m512), i2 = pmul(h0, md.m512);
            st_chunk(wrow + (48 ^ x7), i0, pmul(g4, md.m512), i2, pmul(h4, md.m512));
            st_chunk(wrow + (64 ^ x7), pmul(g0, md.m1024), pmul(h0, md.m1024), pmul(i0, md.m1024), pmul(i2, md.m1024));
        }
        __syncwarp();
        #pragma unroll
        for (int ks = 0; ks < 4; ks++) {
            uint32_t a[4], b[4], c[4], dd[2];
            ldsm4t(a, la + ks * 2048); ldsm4t(b, lb0 + ks * 2048); ldsm4t(c, lb1 + ks * 2048);
            asm volatile("ldmatrix.sync.aligned.m8n8.x2.trans.shared.b16 {%0,%1}, [%2];" : "=r"(dd[0]), "=r"(dd[1]) : "r"(lb2 + ks * 2048) : "memory");
            mma_f16(kd, a, b[0], b[1]); mma_f16(kd + 4, a, b[2], b[3]); mma_f16(kd + 8, a, c[0], c[1]); mma_f16(kd + 12, a, c[2], c[3]); mma_f16(kd + 16, a, dd[0], dd[1]);
        }
        md = md2;
        __syncwarp();
    }
    #pragma unroll
    for (int i = 0; i < 5; i++) sts128(sA + i * 512 + lane * 16, make_uint4(__float_as_uint(kd[4*i]), __float_as_uint(kd[4*i+1]), __float_as_uint(kd[4*i+2]), __float_as_uint(kd[4*i+3])));
    if (lane == 0) sts32(sA + 2560, __float_as_uint(klast * cscale));
    bar_sync(1 + wg, 128);
    const uint32_t sT = sb + SB_T + 64;
    {
        const int lo0 = (g >> 1) + 8 * (g & 1);
        float v[4] = {0.f, 0.f, 0.f, 0.f}, z = 0.f, zl = 0.f;
        #pragma unroll
        for (int w = 0; w < 4; w++) {
            uint4 q = lds128(sb + w * 8192 + warp * 512 + lane * 16);
            v[0] += __uint_as_float(q.x); v[1] += __uint_as_float(q.y); v[2] += __uint_as_float(q.z); v[3] += __uint_as_float(q.w);
            z += lds32f(sb + w * 8192 + 2048 + lane * 16 + warp * 4);
            zl += lds32f(sb + w * 8192 + 2560);
        }
        const int sl = warp < 2 ? 32 : (warp == 2 ? 16 : 8);
        const int i0 = warp < 2 ? 4 * warp + t : (warp == 2 ? 256 + t : 384 + (t & 1) + 64 * (t >> 1));
        const uint32_t ta = sT + 4 * i0 + sl * lo0;
        #pragma unroll
        for (int i = 0; i < 4; i++) { float x = v[i] * kscale; sts32(ta + (i & 1) * 16 * sl + (i >> 1) * 4 * sl, pack_bf16(x, x)); }
        z *= kscale; zl *= kscale;
        sts32(sT + 4 * (512 + 32 * t + 16 * (warp & 1) + 4 * (warp >> 1) + lo0), pack_bf16(z, z));
        if (tw == 0) sts32(sT + 4 * 640, pack_bf16(zl, zl));
    }
    if (warp == 3 && lane < 16) sts32(sb + SB_T + 4 * lane, 0u);
    bar_sync(1 + wg, 128);
    if (gate2) mbar_wait(gate2, 0);
    {
        const uint32_t k0 = sKP + 32, k1 = k0 + 4416;
        {
            int m = 128 + tw;
            uint32_t A = lds32(sT + 4 * (384 + m)), B = lds32(sT + 4 * (385 + m));
            uint32_t X = (m & 1) ? B : A;
            sts128(k0 + m * 16, make_uint4(A, mix(A, X), B, B)); sts128(k1 + m * 16, make_uint4(A, mix(X, B), B, B));
        }
        int m = tw;
        if (warp >= 2) {
            uint32_t A = lds32(sT + 4 * (256 + 2 * m)), B = lds32(sT + 4 * (257 + 2 * m)), C = lds32(sT + 4 * (258 + 2 * m));
            sts128(k0 + m * 16, make_uint4(A, B, mix(B, C), C)); sts128(k1 + m * 16, make_uint4(mix(A, B), B, C, C));
        } else if (warp == 1) {
            uint4 a = lds128(sT + 4 * (128 + 4 * m)); uint32_t a4 = lds32(sT + 4 * (132 + 4 * m));
            sts128(k0 + m * 16, make_uint4(mix(a.x, a.y), a.z, mix(a.z, a.w), a4)); sts128(k1 + m * 16, make_uint4(mix(a.y, a.z), a.z, mix(a.w, a4), a4));
        }
        if (warp == 0 || (warp == 3 && lane < 2)) {
            if (warp == 3) m = lane - 2;
            uint4 a = lds128(sT + 32 * m), b = lds128(sT + 32 * m + 16); uint32_t c0 = lds32(sT + 32 * m + 32), c1 = lds32(sT + 32 * m + 36);
            if (m == 31) c1 = c0;
            sts128(k0 + m * 16, make_uint4(mix(a.y, a.z), mix(a.w, b.x), mix(b.y, b.z), mix(b.w, c0)));
            sts128(k1 + m * 16, make_uint4(mix(a.z, a.w), mix(b.x, b.y), mix(b.z, b.w), mix(c0, c1)));
        }
    }
}

__device__ __forceinline__ void s4d_conv(uint32_t sKP, uint32_t sU, uint32_t dsk, int wg, int warp, int tid) {
    const int tw = tid & 127, lane = tid & 31, g = lane >> 2, t = lane & 3;
    float acc[64];
    #pragma unroll
    for (int i = 0; i < 64; i++) acc[i] = 0.f;
    fence_f<64>(acc);
    {
        uint32_t aaddr = sKP + (g & 1) * 4416 + 4 * ((8 * warp + g + 2 * t) >> 1);
        uint64_t db = mkdesc(sU, 2560, 128, 0);
        uint32_t aA[8], aB[8];
        conv_loadA(aA, aaddr);
        conv_steps<4>(acc, aA, aB, aaddr, db); conv_steps<3>(acc, aA, aB, aaddr, db); conv_steps<2>(acc, aA, aB, aaddr, db); conv_steps<1>(acc, aA, aB, aaddr, db);
    }
    const uint32_t rb = sKP + (warp >> 1) * 4608 + (g + 8 * (warp & 1)) * 288 + t * 8;
    const uint32_t d2 = dsk | (dsk << 16);
    const int al = tw & 63, pl = tw >> 6;
    const uint4 uu[2] = {lds128(sU + pl * 2560 + al * 16), lds128(sU + pl * 2560 + (64 + al) * 16)};
    #pragma unroll
    for (int j = 0; j < 15; j++) { acc[4*j] += acc[4*j+6]; acc[4*j+1] += acc[4*j+7]; }
    #pragma unroll
    for (int h = 0; h < 2; h++) {
        bar_sync(1 + wg, 128);
        #pragma unroll
        for (int j = 0; j < 9; j++) {
            const int q = 4 * (8 * h + j);
            if (q < 64) sts64f(rb + 32 * j, acc[q & 63], acc[(q+1) & 63]); else sts64f(rb + 32 * j, 0.f, 0.f);
        }
        bar_sync(1 + wg, 128);
        const uint32_t uw[4] = {uu[h].x, uu[h].y, uu[h].z, uu[h].w};
        uint32_t res[4];
        #pragma unroll
        for (int i = 0; i < 4; i++) {
            const uint32_t ra = sKP + (15 - 8 * pl - 2 * i) * 288 + al * 4;
            uint32_t y2 = pack_bf16(lds32f(ra) + lds32f(ra + 4612), lds32f(ra - 288) + lds32f(ra - 288 + 4612)), sk;
            asm("mul.rn.bf16x2 %0, %1, %2;" : "=r"(sk) : "r"(uw[i]), "r"(d2));
            asm("add.rn.bf16x2 %0, %1, %2;" : "=r"(res[i]) : "r"(y2), "r"(sk));
        }
        sts128(sU + (64 * h + al) * 32 + pl * 16, make_uint4(res[0], res[1], res[2], res[3]));
    }
    PROXY_FENCE;
}

constexpr int GROUP_BYTES = 32768;
__device__ __forceinline__ void exp_phase1(float* s, uint32_t mant_mask, uint32_t c2) {
    #pragma unroll
    for (int i = 0; i < 16; i++) {
        if (i & 1) {
            uint32_t A = __byte_perm(__float_as_uint(s[2*i]), __float_as_uint(s[2*i+1]), 0x5410);
            uint32_t F, m;
            asm("lop3.b32 %0, %1, %2, 0x3FC03FC0, 0x6A;" : "=r"(F) : "r"(A), "r"(mant_mask));
            asm("fma.rn.bf16x2 %0, %1, %2, %3;" : "=r"(m) : "r"(F), "r"(c2), "r"(0x8d808d80u));
            asm("fma.rn.bf16x2 %0, %1, %2, %3;" : "=r"(m) : "r"(m), "r"(F), "r"(0x0e0b0e0bu));
            s[2*i] = __uint_as_float(A); s[2*i+1] = __uint_as_float(m);
        } else {
            s[2*i] = ex2f(s[2*i]); s[2*i+1] = ex2f(s[2*i+1]);
        }
    }
}
__device__ __forceinline__ void exp_phase2(const float* s, uint32_t* p) {
    #pragma unroll
    for (int i = 0; i < 16; i++) {
        if (i & 1) p[i] = __float_as_uint(s[2*i]) + __float_as_uint(s[2*i+1]);
        else p[i] = pack_bf16(s[2*i], s[2*i+1]);
    }
}
__device__ __forceinline__ void qk(float* s, const uint32_t* qf, uint64_t d) {
    wg_bf16_n64_rs<0>(s, qf[0], qf[1], qf[2], qf[3], d, 0);
    wg_bf16_n64_rs<0>(s, qf[4], qf[5], qf[6], qf[7], d + 128, 1);
}
__device__ __forceinline__ void pv(float* o, const uint32_t* p, uint64_t d) {
    #pragma unroll
    for (int j = 0; j < 4; j++) wg_bf16_n32_rs<1>(o, p[4*j], p[4*j+1], p[4*j+2], p[4*j+3], d + j * 16, 1);
}


__device__ __forceinline__ void kv_load(uint32_t sbase, uint32_t bars, int grp) {
    mbar_expect_tx(bars + B_KVF + 8 * (grp & 3), GROUP_BYTES);
    bulk_g2s(sbase + (grp & 3) * GROUP_BYTES, g_KV + (size_t)((grp + blockIdx.x) & 7) * GROUP_BYTES, GROUP_BYTES, bars + B_KVF + 8 * (grp & 3));
}
__device__ __forceinline__ void wo_load(uint32_t dst, const CUtensorMap* mwo, int col0, uint32_t bar, int lane) {
    if (lane == 0) {
        PROXY_FENCE;
        mbar_expect_tx(bar, 65536);
        asm volatile("cp.async.bulk.tensor.3d.shared::cluster.global.mbarrier::complete_tx::bytes [%0], [%1, {%3, %4, %4}], [%2];" :: "r"(dst), "l"(mwo), "r"(bar), "r"(col0), "r"(0) : "memory");
    }
    __syncwarp();
}

__device__ __forceinline__ bool conv_try(uint32_t bars, int ch, int grp, int gmin, int wg) {
    int got = grp >= FORCE || (grp >= gmin && mbar_test(bars + B_KG + 8 * ch, 0) && mbar_test(bars + B_KG, 0) && mbar_test(bars + B_UL, 0)), any;
    asm volatile("{.reg .pred p, q; setp.ne.s32 p, %1, 0; barrier.cta.red.or.pred q, %2, 128, p; selp.s32 %0, 1, 0, q;}" : "=r"(any) : "r"(got), "r"(1 + wg) : "memory");
    return __shfl_sync(0xffffffffu, any, 0) != 0;
}

__global__ void __launch_bounds__(640, 1) k_fused(const __grid_constant__ CUtensorMap mx, const __grid_constant__ CUtensorMap mwq,
                                                  const __grid_constant__ CUtensorMap mwo, const __grid_constant__ CUtensorMap mu,
                                                  const __grid_constant__ CUtensorMap myt, const __grid_constant__ CUtensorMap mout,
                                                  const __grid_constant__ CUtensorMap mut, const Params p) {
    extern __shared__ __align__(1024) uint8_t smem[];
    const uint32_t sbase = smem_u32(smem), bars = sbase + SM_BAR;
    const int tid = threadIdx.x, blk = blockIdx.x < 4 ? 128 + blockIdx.x : blockIdx.x - 4;
    const bool extra = blk >= 128, heavy = blk < 64;
    const int qb = blk >> 3, r = blk & 7;
    const int tw = tid & 127, lane = tid & 31, g = lane >> 2, t = lane & 3;
    const int wg = __shfl_sync(0xffffffffu, tid >> 7, 0), warp = __shfl_sync(0xffffffffu, (tid >> 5) & 3, 0);
    const int og = 2 * qb + (r >> 2), ocol = 112 * (r & 3);
    if (wg == 4) {
        asm volatile("setmaxnreg.dec.sync.aligned.u32 32;");
        unsigned ticket = 0;
        if (tw == 64) { mbar_init(bars + B_PB, 1); asm volatile("fence.mbarrier_init.release.cluster;" ::: "memory"); ticket = atomicInc(&g_ticket, 263u); }
        if (extra) {
            bar_sync(6, 128);
            asm volatile("bar.arrive 8, 640;" ::: "memory");
            if (tw == 64) { sts32(bars + B_PAR, ticket >= 132u ? 2048u : 0u); mbar_arrive(bars + B_PB); }
            if (blk == 128) {
                mbar_wait(bars + B_PB, 0);
                uint4* z = (uint4*)(g_cnt + (lds32(bars + B_PAR) ^ 2048u));
                #pragma unroll 1
                for (int i = tw; i < 512; i += 128) z[i] = make_uint4(0, 0, 0, 0);
            }
        } else {
            if (tw == 0) {
                #pragma unroll
                for (int i = 0; i < 7; i++) mbar_init(bars + B_XF + 8 * i, 1);
                asm volatile("fence.mbarrier_init.release.cluster;" ::: "memory");
                #pragma unroll 1
                for (int c = 0; c < 7; c++) { mbar_expect_tx(bars + B_XF + 8 * c, 16384); tma2d(sbase + c * 16384, &mx, c * 64, qb * 128, bars + B_XF + 8 * c); }
            }
            if (tw == 96) {
                mbar_init(bars + B_UF, 1); mbar_init(bars + B_WQF, 1);
                asm volatile("fence.mbarrier_init.release.cluster;" ::: "memory");
                asm volatile("prefetch.tensormap [%0];" :: "l"(&mwq) : "memory");
                mbar_expect_tx(bars + B_UF, 16384);
                tma2d(sbase + SM_QS, &mu, 56 * r, qb * 128, bars + B_UF);
            }
            if (tw == 32) {
                mbar_init(bars + B_KVW, 4); mbar_init(bars + B_PD, 4); mbar_init(bars + B_QR, 5); mbar_init(bars + B_UL, 2); mbar_init(bars + B_WF, 2);
                #pragma unroll
                for (int i = 0; i < 4; i++) { mbar_init(bars + B_KG + 8*i, i < 3 ? 4 : 1); mbar_init(bars + B_BD + 8*i, 4); mbar_init(bars + B_KVF + 8*i, 1); mbar_init(bars + B_KVE + 8*i, 16); }
                #pragma unroll
                for (int i = 0; i < 8; i++) mbar_init(bars + B_OF + 8*i, 1);
                mbar_init(bars + B_YF, 1); mbar_init(bars + B_QF, 1); mbar_init(bars + B_UT, 8); mbar_init(bars + B_OP, 4); mbar_init(bars + B_KS, 1);
                asm volatile("fence.mbarrier_init.release.cluster;" ::: "memory");
            }
            bar_sync(6, 128);
            asm volatile("bar.arrive 8, 640;" ::: "memory");
            if (tw == 96) {
                mbar_wait(bars + B_XF, 0);
                mbar_expect_tx(bars + B_WQF, 57344);
                tma2d(sbase + SM_W, &mwq, 56 * r, 0, bars + B_WQF); tma2d(sbase + SM_W + 28672, &mwq, 56 * r, 224, bars + B_WQF);
            }
            if (tw == 32) {
                asm volatile("prefetch.tensormap [%0];" :: "l"(&mut) : "memory"); asm volatile("prefetch.tensormap [%0];" :: "l"(&mwo) : "memory");
                asm volatile("prefetch.tensormap [%0];" :: "l"(&myt) : "memory"); asm volatile("prefetch.tensormap [%0];" :: "l"(&mout) : "memory");
            }
            if (tw == 64) { sts32(bars + B_PAR, ticket >= 132u ? 2048u : 0u); mbar_arrive(bars + B_PB); }
            mbar_wait(bars + B_PB, 0);
            unsigned* const cnt = g_cnt + lds32(bars + B_PAR);
            if (warp == 0) {
                if (lane == 0) {
                    mbar_wait(bars + B_KVW, 0);
                    bulk_s2g(g_KV + (qb * 2) * 8192 + r * 1024, sbase + SM_KVW, 1024); bulk_s2g(g_KV + (qb * 2 + 1) * 8192 + r * 1024, sbase + SM_KVW + 1024, 1024);
                    uint4 gm = lds128(bars + B_CMAX + 48);
                    asm volatile("red.relaxed.gpu.global.max.u32 [%0], %1;" :: "l"(CNT(0) + (r < 4 ? 1 + r : 5)), "r"(max(max(gm.x, gm.y), max(gm.z, gm.w))) : "memory");
                    bulk_publish(CNT(0));
                    mbar_arrive(bars + B_KS);
                    mbar_wait(bars + B_PD, 0);
                }
                __syncwarp();
                {
                    unsigned v = 0;
                    int it = 0;
                    #pragma unroll 1
                    for (; it < (1 << 22); it++) {
                        asm volatile("ld.relaxed.gpu.global.u32 %0, [%1];" : "=r"(v) : "l"(CNT(0) + (lane & 7)) : "memory");
                        if (__shfl_sync(0xffffffffu, v, 0) >= 128) break;
                        __nanosleep(100);
                    }
                    if (it == (1 << 22)) __trap();
                    v = ld_acquire(CNT(0) + (lane & 7));
                    if (lane == 0) kv_load(sbase, bars, 0);
                    if (lane < 8) sts32(bars + B_GMAX + 4 * lane, v);
                }
                __syncwarp();
                if (lane == 0) {
                    mbar_arrive(bars + B_QR);
                    kv_load(sbase, bars, 1);
                    #pragma unroll 1
                    for (int gi = 4; gi < 8; gi++) { mbar_wait(bars + B_KVE + 8 * (gi - 4), 0); kv_load(sbase, bars, gi); }
                }
                __syncwarp();
                mbar_wait(bars + B_KVE, 1); mbar_wait(bars + B_KVE + 8, 1);
                wo_load(sbase + SM_WO1, &mwo, ocol + 56, bars + B_WF, lane);
                {
                    bool done = lane >= 8;
                    #pragma unroll 1
                    for (int it = 0; ; it++) {
                        unsigned v;
                        asm volatile("ld.relaxed.gpu.global.u32 %0, [%1];" : "=r"(v) : "l"(CNT(32 + og) + (lane & 7)) : "memory");
                        if (!done && v >= 2 && mbar_test(bars + B_KVE + 16 + 8 * (lane >> 2), 1)) {
                            mbar_expect_tx(bars + B_OF + 8 * lane, 8192);
                            bulk_g2s(sbase + SM_OT + lane * 8192, g_O + (size_t)(og * 8 + lane) * 8192, 8192, bars + B_OF + 8 * lane);
                            done = true;
                        }
                        if (__all_sync(0xffffffffu, done)) break;
                        if (it > (1 << 22)) __trap();
                    }
                }
            } else {
                const int w = warp - 1;
                if (warp == 1) {
                    if (lane == 0) {
                        mbar_wait(bars + B_QR, 0);
                        #pragma unroll 1
                        for (int i = 1; i < 3; i++) { mbar_wait(bars + B_KG + 8 * i, 0); PROXY_FENCE; kv_load(sbase, bars, 1 + i); }
                        #pragma unroll 1
                        for (int k = 0; k < (heavy ? 4 : 3); k++) {
                            const int i = k == 1 ? 2 : (k == 2 ? 1 : k);
                            mbar_wait(bars + B_BD + 8 * i, 0);
                            bulk_s2g(g_YT + (size_t)(i < 3 ? 3 * blk + i : 384 + blk) * S_, sbase + SM_U0 + i * 5120, 4096);
                            bulk_publish(CNT(3));
                        }
                    }
                    __syncwarp();
                    wo_load(sbase + SM_WO0, &mwo, ocol, bars + B_WF, lane);
                } else {
                    if (warp == 2) {
                        if (lane == 0) {
                            mbar_wait(bars + B_UT, 0);
                            asm volatile("cp.async.bulk.tensor.3d.global.shared::cta.bulk_group [%0, {%2, %3, %4}], [%1];"
                                         :: "l"(&mut), "r"(sbase + SM_QS), "r"((15 - qb) * 64), "r"(0), "r"(56 * r) : "memory");
                            asm volatile("cp.async.bulk.commit_group;\n cp.async.bulk.wait_group.read 0;" ::: "memory");
                            mbar_arrive(bars + B_QF);
                            bulk_publish(CNT(2));
                            spin_until(CNT(2), 128);
                            mbar_wait(bars + B_PD, 0);
                            mbar_expect_tx(bars + B_UL, heavy ? 16384 : 12288);
                            #pragma unroll 1
                            for (int i = 0; i < (heavy ? 8 : 6); i++)
                                bulk_g2s(sbase + SM_U0 + i * 2560, g_UT + (size_t)(i < 6 ? 3 * blk : 381 + blk) * S_ + i * 1024, 2048, bars + B_UL);
                        }
                    } else {
                        mbar_wait(bars + B_PD, 0);
                        #pragma unroll 1
                        for (int i = 0; i < 8; i++) sts128(sbase + SM_U0 + i * 2560 + 2048 + lane * 16, make_uint4(0, 0, 0, 0));
                        PROXY_FENCE;
                        warp_arrive(bars + B_UL, lane);
                        if (heavy && lane == 0) {
                            mbar_wait(bars + B_BD, 0);
                            spin_until(CNT(4) + blk, 1);
                            PROXY_FENCE;
                            mbar_expect_tx(bars + B_KG + 24, 8832);
                            bulk_g2s(sbase + SM_KP3, g_KP + (size_t)blk * 9216, 8832, bars + B_KG + 24);
                        }
                    }
                }
                if (warp == 2 && lane == 0) {
                    spin_until(CNT(3), 448);
                    PROXY_FENCE;
                    mbar_expect_tx(bars + B_YF, 14336);
                    tma2d(sbase + SM_YT, &myt, 1984 - og * 64, ocol, bars + B_YF);
                }
                mbar_wait(bars + B_YF, 0);
                mbar_wait(bars + B_OP, 0);
                {
                    const int crow = 8 * ((lane & 7) >> 1) + 2 * (lane >> 3) + (lane & 1);
                    #pragma unroll 1
                    for (int i = w; i < 32; i += 3) {
                        const int cb = i >> 3, c = i & 7;
                        uint32_t rg[4];
                        ldsm4t(rg, sbase + SM_YT + (cb * 32 + crow) * 128 + ((c ^ (crow & 7)) << 4));
                        if (cb < 3 || t < 2) sts128(sbase + SM_YS + (63 - (c * 8 + g)) * 224 + cb * 64 + t * 16, make_uint4(rg[0], rg[1], rg[2], rg[3]));
                    }
                    PROXY_FENCE;
                    bar_sync(5, 96);
                    if (warp == 1 && lane == 0) tma2d_store(&mout, 448 + ocol, og * 64, sbase + SM_YS);
                }
            }
        }
    } else {
    const bool proj = !extra && wg == 3;
    int d = extra ? 384 + (blk - 128) * 4 + wg : 3 * blk + wg;
    s4d_in in = {};
    uint4 kvw[4];
    if (!proj) in = s4d_load(p, d, tw);
    else {
        const bf16* src = (r < 4 ? p.wk : p.wv) + 8 * (r & 3) + tw * 28;
        #pragma unroll
        for (int i = 0; i < 4; i++) {
            uint2 a = make_uint2(0, 0), b = make_uint2(0, 0);
            if (i < 3 || tw < 64) { a = __ldg((const uint2*)(src + i * 128 * 28)); if ((r & 3) != 3) b = __ldg((const uint2*)(src + i * 128 * 28 + 4)); }
            kvw[i] = make_uint4(a.x, a.y, b.x, b.y);
        }
    }
    asm volatile("setmaxnreg.inc.sync.aligned.u32 112;");
    bar_sync(8, 640);
    if (proj) {
        #pragma unroll
        for (int i = 0; i < 4; i++) if (i < 3 || tw < 64) sts128(sbase + SM_KVW + (tw + 128 * i) * 16, kvw[i]);
        PROXY_FENCE;
        bar_sync(4, 128);
        {
            float ka[8];
            #pragma unroll
            for (int i = 0; i < 8; i++) ka[i] = 0.f;
            fence_f<8>(ka);
            uint64_t da = mkdesc(sbase, 16, 1024, 1), db = mkdesc(sbase + SM_KVW, 128, 16, 0);
            #pragma unroll 1
            for (int c = 0; c < 7; c++) {
                mbar_wait(bars + B_XF + 8 * c, 0);
                WG_FENCE;
                #pragma unroll
                for (int ks = 0; ks < 4; ks++) {
                    wg_bf16_n8_ss<0, 1>(ka, da + ks * 2, db + ks * 16, 1);
                    wg_bf16_n8_ss<0, 1>(ka + 4, da + 512 + ks * 2, db + ks * 16, 1);
                }
                WG_COMMIT;
                da += 1024; db += 64;
            }
            WG_WAIT(0);
            fence_f<8>(ka);
            bar_sync(4, 128);
            float gm = 0.f;
            #pragma unroll
            for (int mh = 0; mh < 2; mh++)
                #pragma unroll
                for (int hh = 0; hh < 2; hh++) {
                    uint32_t v = pack_bf16(ka[4*mh + 2*hh], ka[4*mh + 2*hh + 1]);
                    float a = bf_lo(v), b = bf_hi(v);
                    float n2 = a * a + b * b;
                    if ((r & 3) == 3 && t >= 2) v = (r == 3) ? 0x3F803F80u : (t == 2 ? 0x00003F80u : 0u);
                    sts32(sbase + SM_KVW + mh * 1024 + (warp * 16 + g + 8 * hh) * 16 + t * 4, v);
                    n2 += __shfl_xor_sync(0xffffffffu, n2, 1); n2 += __shfl_xor_sync(0xffffffffu, n2, 2);
                    gm = fmaxf(gm, n2);
                    if (!(n2 == n2)) gm = INFINITY;
                }
            uint32_t gmu = __reduce_max_sync(0xffffffffu, __float_as_uint(gm));
            if (lane == 0) sts32(bars + B_CMAX + 48 + 4 * warp, gmu);
            PROXY_FENCE;
            warp_arrive(bars + B_KVW, lane);
        }
        float acc[56];
        #pragma unroll
        for (int i = 0; i < 56; i++) acc[i] = 0.f;
        fence_f<56>(acc);
        mbar_wait(bars + B_WQF, 0);
        {
            uint64_t da = mkdesc(sbase, 16, 1024, 1), db = mkdesc(sbase + SM_W, 16, 1024, 1);
            WG_FENCE;
            #pragma unroll 1
            for (int c = 0; c < 7; c++) {
                #pragma unroll
                for (int ks = 0; ks < 4; ks++) {
                    wg_bf16_n56_ss<0, 1>(acc, da + ks * 2, db + ks * 128, 1);
                    wg_bf16_n56_ss<0, 1>(acc + 28, da + 512 + ks * 2, db + ks * 128, 1);
                }
                da += 1024; db += 512;
            }
            WG_COMMIT;
            WG_WAIT(0);
            fence_f<56>(acc);
        }
        if (lane == 0) mbar_arrive(bars + B_PD);
        mbar_wait(bars + B_QF, 0);
        #pragma unroll
        for (int mh = 0; mh < 2; mh++)
            #pragma unroll
            for (int j = 0; j < 7; j++) {
                int c = 8 * j + 2 * t, h = c >= 28 ? 1 : 0;
                uint32_t a = sbase + SM_QS + (mh * 2 + h) * 4096 + (warp * 16 + g) * 56 + (c - 28 * h) * 2;
                sts32(a, pack_bf16(acc[28*mh + 4*j] * QSCALE, acc[28*mh + 4*j + 1] * QSCALE));
                sts32(a + 8 * 56, pack_bf16(acc[28*mh + 4*j + 2] * QSCALE, acc[28*mh + 4*j + 3] * QSCALE));
            }
        warp_arrive(bars + B_QR, lane);
    }
    else {
        if (!extra && wg) {
            const int h = warp & 1, rq = warp >> 1;
            const int row = 127 - (16 * (4 * rq + ((lane & 7) >> 1)) + 8 * h + 2 * (lane >> 3) + (lane & 1));
            mbar_wait(bars + B_UF, 0);
            uint32_t rg[4][4];
            #pragma unroll
            for (int k = 0; k < 4; k++) ldsm4t(rg[k], sbase + SM_QS + row * 128 + (((2 * k + wg - 1) ^ (row & 7)) << 4));
            bar_sync(9, 256);
            #pragma unroll
            for (int k = 0; k < 4; k++)
                sts128(sbase + SM_QS + ((2 * k + wg - 1) * 8 + g) * 256 + h * 128 + (4 * rq + t) * 16, make_uint4(rg[k][0], rg[k][1], rg[k][2], rg[k][3]));
            PROXY_FENCE;
            warp_arrive(bars + B_UT, lane);
        }
        const int nit = (extra || (wg == 0 && (blk >> 5) == 2)) ? 2 : 1;
        #pragma unroll 1
        for (int it = 0; it < nit; it++) {
            const s4d_in cur = in;
            const bool exp_kp = extra || it == 1;
            const int dn = extra ? d + 16 : 352 + blk;
            if (it + 1 < nit) in = s4d_load(p, dn, tw);
            const uint32_t sb = sbase + (extra ? wg * 32768 : (wg == 0 ? SM_SC0 : (1 + wg) * 32768));
            const uint32_t sKP = exp_kp ? sb + 8192 : sbase + (wg == 0 ? SM_KP0 : SM_KP1 + (wg - 1) * 9216);
            auto gate = [&]() {
                if (!extra && wg) {
                    mbar_wait(bars + B_PD, 0);
                }
            };
            s4d_kgen(cur, sb, sKP, bars + B_CMAX + 16 * wg, gate, (!extra && !wg) ? bars + B_KS : 0u, wg, warp, tid);
            if (exp_kp) {
                PROXY_FENCE;
                bar_sync(1 + wg, 128);
                mbar_wait(bars + B_PB, 0);
                if (tw == 0) { unsigned* const cnt = g_cnt + lds32(bars + B_PAR); bulk_s2g(g_KP + (size_t)(d - 384) * 9216, sKP, 8832); bulk_publish(CNT(4) + (d - 384)); }
            }
            d = dn;
        }
        if (!extra) warp_arrive(bars + B_KG + 8 * wg, lane);
    }
    if (!extra) {
        const bool dbl = (blk >> 5) == 2;
        const int ch = wg == 3 ? 2 : (wg == 2 ? (dbl ? 0 : 3) : wg);
        bool pending = wg == 0 ? !dbl : (ch < 3 || heavy);
        const int gmin = wg == 0 ? GM0 : (wg == 3 ? GM3 : GM1);
        const uint32_t osv = sbase + SM_OSV + wg * 8192 + tw * 4;
        float m0 = -INFINITY, m1 = -INFINITY;
        const uint64_t dbase = mkdesc(sbase, 1024, 128, 0), dvoff = mkdesc(4096, 128, 1024, 0) - mkdesc(0, 1024, 128, 0);
        float o[16];
        int grp = 0;
        mbar_wait(bars + B_QR, 0);
        bool unsafe;
        #pragma unroll 1
        for (int seg = 0; ; seg++) {
            uint32_t qf[8];
            {
                uint32_t qa = sbase + SM_QS + wg * 4096 + (warp * 16 + g) * 56 + t * 4;
                #pragma unroll
                for (int c = 0; c < 4; c++) {
                    bool ok = c < 3 || t < 2;
                    qf[2*c] = ok ? lds32(qa + c * 16) : 0u;
                    qf[2*c+1] = ok ? lds32(qa + 8 * 56 + c * 16) : 0u;
                }
            }
            if (seg == 0) {
                #pragma unroll
                for (int i = 0; i < 16; i++) o[i] = 0.f;
                {
                    float vm = lds32f(bars + B_GMAX + 20);
                    float b0 = 0.f, b1 = 0.f;
                    #pragma unroll
                    for (int c = 0; c < 4; c++) {
                        float km = lds32f(bars + B_GMAX + 4 + 4 * c);
                        float a = bf_lo(qf[2*c]), b = bf_hi(qf[2*c]), cc = bf_lo(qf[2*c+1]), dd = bf_hi(qf[2*c+1]);
                        float n0 = a*a + b*b, n1 = cc*cc + dd*dd;
                        n0 += __shfl_xor_sync(0xffffffffu, n0, 1); n0 += __shfl_xor_sync(0xffffffffu, n0, 2);
                        n1 += __shfl_xor_sync(0xffffffffu, n1, 1); n1 += __shfl_xor_sync(0xffffffffu, n1, 2);
                        float r0, r1;
                        asm("sqrt.approx.f32 %0, %1;" : "=f"(r0) : "f"(n0 * km)); asm("sqrt.approx.f32 %0, %1;" : "=f"(r1) : "f"(n1 * km));
                        b0 += r0; b1 += r1;
                    }
                    int bad = !(b0 <= 90.f && b1 <= 90.f && vm <= 1e12f && vm >= 1e-12f), any;
                    asm volatile("{.reg .pred p, q; setp.ne.s32 p, %1, 0; barrier.cta.red.or.pred q, %2, 128, p; selp.s32 %0, 1, 0, q;}" : "=r"(any) : "r"(bad), "r"(1 + wg) : "memory");
                    unsafe = __shfl_sync(0xffffffffu, any, 0) != 0;
                }
            } else {
                #pragma unroll
                for (int i = 0; i < 16; i++) o[i] = lds32f(osv + i * 512);
                warp_arrive(bars + B_BD + 8 * ch, lane);
            }
            if (!unsafe && t == 2) qf[7] = 0x42C747C0u;
            float s0[32];
            uint32_t p0[16];
            #pragma unroll
            for (int i = 0; i < 16; i++) p0[i] = 0;
            #pragma unroll
            for (int i = 0; i < 32; i++) s0[i] = 0.f;
            uint32_t mmask = 0x007F007Fu, c2 = 0x0ca90ca9u;
            asm volatile("" : "+r"(mmask), "+r"(c2));
            fence_f<16>(o); fence_f<32>(s0); fence_r<8>(qf); fence_r<16>(p0);
            const int g0 = grp;
            uint64_t dprevV = dbase + dvoff + (uint64_t)((grp & 3) * 2048);
            bool stop = false;
            if (!unsafe) {
                #pragma unroll 1
                do {
                    uint64_t dst = dbase + (uint64_t)((grp & 3) * 2048);
                    mbar_wait(bars + B_KVF + 8 * (grp & 3), grp >> 2);
                    #pragma unroll 1
                    for (int ti = 0; ti < 4; ti++) {
                        WG_FENCE;
                        qk(s0, qf, dst);
                        WG_COMMIT;
                        pv(o, p0, dprevV);
                        WG_COMMIT;
                        WG_WAIT(1);
                        fence_f<32>(s0);
                        exp_phase1(s0, mmask, c2);
                        fence_f<32>(s0);
                        WG_WAIT(0);
                        fence_f<32>(s0);
                        exp_phase2(s0, p0);
                        fence_r<16>(p0);
                        dprevV = dst + dvoff;
                        dst += 512;
                        if (ti == 0 && grp > g0 && lane == 0) mbar_arrive(bars + B_KVE + 8 * ((grp - 1) & 3));
                    }
                    grp++;
                    if (pending) stop = conv_try(bars, ch, grp, gmin, wg);
                } while (grp < 8 && !stop);
                WG_FENCE;
                pv(o, p0, dprevV);
                WG_COMMIT;
                WG_WAIT(0);
                fence_f<16>(o);
            } else {
                #pragma unroll 1
                do {
                    uint64_t dst = dbase + (uint64_t)((grp & 3) * 2048);
                    mbar_wait(bars + B_KVF + 8 * (grp & 3), grp >> 2);
                    if (grp > g0 && lane == 0) mbar_arrive(bars + B_KVE + 8 * ((grp - 1) & 3));
                    #pragma unroll 1
                    for (int ti = 0; ti < 4; ti++) {
                        WG_FENCE;
                        qk(s0, qf, dst);
                        WG_COMMIT;
                        WG_WAIT(0);
                        fence_f<32>(s0);
                        float a0 = m0, a1 = m1;
                        #pragma unroll
                        for (int j = 0; j < 8; j++) { a0 = fmaxf(a0, fmaxf(s0[4*j], s0[4*j+1])); a1 = fmaxf(a1, fmaxf(s0[4*j+2], s0[4*j+3])); }
                        a0 = fmaxf(a0, __shfl_xor_sync(0xffffffffu, a0, 1)); a0 = fmaxf(a0, __shfl_xor_sync(0xffffffffu, a0, 2));
                        a1 = fmaxf(a1, __shfl_xor_sync(0xffffffffu, a1, 1)); a1 = fmaxf(a1, __shfl_xor_sync(0xffffffffu, a1, 2));
                        float f0 = ex2f(m0 - a0), f1 = ex2f(m1 - a1);
                        m0 = a0; m1 = a1;
                        #pragma unroll
                        for (int j = 0; j < 4; j++) { o[4*j] *= f0; o[4*j+1] *= f0; o[4*j+2] *= f1; o[4*j+3] *= f1; }
                        #pragma unroll
                        for (int j = 0; j < 8; j++) {
                            p0[2*j] = pack_bf16(ex2f(s0[4*j] - m0), ex2f(s0[4*j+1] - m0));
                            p0[2*j+1] = pack_bf16(ex2f(s0[4*j+2] - m1), ex2f(s0[4*j+3] - m1));
                        }
                        fence_r<16>(p0); fence_f<16>(o);
                        WG_FENCE;
                        pv(o, p0, dst + dvoff);
                        WG_COMMIT;
                        WG_WAIT(0);
                        fence_f<16>(o);
                        dst += 512;
                    }
                    grp++;
                    if (pending) stop = conv_try(bars, ch, grp, gmin, wg);
                } while (grp < 8 && !stop);
            }
            if (lane == 0) mbar_arrive(bars + B_KVE + 8 * ((grp - 1) & 3));
            if (!stop) break;
            mbar_wait(bars + B_KG, 0);
            #pragma unroll
            for (int i = 0; i < 16; i++) sts32(osv + i * 512, __float_as_uint(o[i]));
            pending = false;
            mbar_wait(bars + B_KG + 8 * ch, 0); mbar_wait(bars + B_UL, 0);
            const int dd = ch < 3 ? 3 * blk + ch : 384 + blk;
            const uint32_t sKP = sbase + (ch == 0 ? SM_KP0 : (ch == 3 ? SM_KP3 : SM_KP1 + (ch - 1) * 9216));
            s4d_conv(sKP, sbase + SM_U0 + ch * 5120, __ldg((const unsigned short*)p.dsk + dd), wg, warp, tid);
        }
        {
            float l0 = __shfl_sync(0xffffffffu, o[12], (lane & ~3) | 2);
            float l1 = __shfl_sync(0xffffffffu, o[14], (lane & ~3) | 2);
            float r0 = __frcp_rn(l0), r1 = __frcp_rn(l1);
            const uint32_t ob = sbase + SM_QS + wg * 4096 + (warp * 16 + g) * 64 + t * 4;
            bar_sync(1 + wg, 128);
            #pragma unroll
            for (int j = 0; j < 4; j++) {
                const bool ok = j < 3 || t < 2;
                const uint32_t a = ob + ((j ^ (g >> 1)) << 4);
                sts32(a, ok ? pack_bf16(o[4*j]*r0, o[4*j+1]*r0) : 0u);
                sts32(a + 512, ok ? pack_bf16(o[4*j+2]*r1, o[4*j+3]*r1) : 0u);
            }
            PROXY_FENCE;
            bar_sync(1 + wg, 128);
            if (tw == 0) {
                unsigned* const cnt = g_cnt + lds32(bars + B_PAR);
                bulk_s2g(g_O + (size_t)((2 * qb + (wg >> 1)) * 16 + 2 * r + (wg & 1)) * 4096, sbase + SM_QS + wg * 4096, 4096);
                bulk_publish(CNT(32 + 2 * qb + (wg >> 1)) + r);
                mbar_arrive(bars + B_OP);
            }
        }
        if (wg >= 2) {
            mbar_wait(bars + B_WF, 0);
            float acc[28];
            #pragma unroll
            for (int i = 0; i < 28; i++) acc[i] = 0.f;
            fence_f<28>(acc);
            const uint64_t da = mkdesc(sbase + SM_OT, 16, 512, 2), db = mkdesc(sbase + ((wg & 1) ? SM_WO1 : SM_WO0), 16, 1024, 1);
            #pragma unroll 1
            for (int i = 0; i < 8; i++) {
                const int c = i;
                mbar_wait(bars + B_OF + 8*c, 0);
                WG_FENCE;
                #pragma unroll
                for (int ks = 0; ks < 4; ks++) wg_bf16_n56_ss<0, 1>(acc, da + c * 512 + (ks >> 1) * 256 + (ks & 1) * 2, db + c * 512 + ks * 128, 1);
                WG_COMMIT;
            }
            WG_WAIT(0);
            fence_f<28>(acc);
            const uint32_t oa = sbase + SM_OT + (warp * 16 + g) * 224 + (wg & 1) * 112 + t * 4;
            bar_sync(7, 256);
            #pragma unroll
            for (int j = 0; j < 7; j++) { sts32(oa + 16 * j, pack_bf16(acc[4*j], acc[4*j+1])); sts32(oa + 8 * 224 + 16 * j, pack_bf16(acc[4*j+2], acc[4*j+3])); }
            PROXY_FENCE;
            bar_sync(7, 256);
            if (tid == 256) tma2d_store(&mout, ocol, og * 64, sbase + SM_OT);
        }
    }
    }
}

typedef CUresult (*EncFn)(CUtensorMap*, CUtensorMapDataType, cuuint32_t, void*, const cuuint64_t*, const cuuint64_t*, const cuuint32_t*, const cuuint32_t*, CUtensorMapInterleave, CUtensorMapSwizzle, CUtensorMapL2promotion, CUtensorMapFloatOOBfill);
static void mk_map(EncFn enc, CUtensorMap* m, const void* ptr, int rows, int b0, int b1, CUtensorMapSwizzle sw) {
    cuuint64_t gd[2] = {448, (cuuint64_t)rows}; cuuint64_t gs[1] = {896}; cuuint32_t bx[2] = {(cuuint32_t)b0, (cuuint32_t)b1}; cuuint32_t es[2] = {1, 1};
    enc(m, CU_TENSOR_MAP_DATA_TYPE_BFLOAT16, 2, (void*)ptr, gd, gs, bx, es, CU_TENSOR_MAP_INTERLEAVE_NONE, sw, CU_TENSOR_MAP_L2_PROMOTION_L2_128B, CU_TENSOR_MAP_FLOAT_OOB_FILL_NONE);
}

extern "C" void kernel_launch(void* const* d_in, const int* in_sizes, int n_in, void* d_out, int out_size) {
    static EncFn enc = nullptr;
    static void *yt_ptr = nullptr, *ut_ptr = nullptr;
    if (!enc) {
        void* fn = nullptr; cudaDriverEntryPointQueryResult qr;
        cudaGetDriverEntryPoint("cuTensorMapEncodeTiled", &fn, cudaEnableDefault, &qr);
        enc = (EncFn)fn;
        cudaGetSymbolAddress(&yt_ptr, g_YT); cudaGetSymbolAddress(&ut_ptr, g_UT);
        cudaFuncSetAttribute(k_fused, cudaFuncAttributeMaxDynamicSharedMemorySize, SM_TOTAL);
    }
    CUtensorMap mx, mwq, mwo, mu, myt, mout, mut;
    mk_map(enc, &mx, d_in[0], 2048, 64, 128, CU_TENSOR_MAP_SWIZZLE_128B);
    mk_map(enc, &mwq, d_in[1], 448, 64, 224, CU_TENSOR_MAP_SWIZZLE_128B);
    {
        cuuint64_t gd[3] = {448, 28, 16}; cuuint64_t gs[2] = {896, 28 * 896}; cuuint32_t bx[3] = {64, 32, 16}; cuuint32_t es[3] = {1, 1, 1};
        enc(&mwo, CU_TENSOR_MAP_DATA_TYPE_BFLOAT16, 3, d_in[4], gd, gs, bx, es, CU_TENSOR_MAP_INTERLEAVE_NONE, CU_TENSOR_MAP_SWIZZLE_128B, CU_TENSOR_MAP_L2_PROMOTION_L2_128B, CU_TENSOR_MAP_FLOAT_OOB_FILL_NONE);
    }
    mk_map(enc, &mu, d_in[5], 2048, 64, 128, CU_TENSOR_MAP_SWIZZLE_128B);
    {
        cuuint64_t gd[2] = {2048, 448}; cuuint64_t gs[1] = {4096}; cuuint32_t bx[2] = {64, 112}; cuuint32_t es[2] = {1, 1};
        enc(&myt, CU_TENSOR_MAP_DATA_TYPE_BFLOAT16, 2, yt_ptr, gd, gs, bx, es, CU_TENSOR_MAP_INTERLEAVE_NONE, CU_TENSOR_MAP_SWIZZLE_128B, CU_TENSOR_MAP_L2_PROMOTION_L2_128B, CU_TENSOR_MAP_FLOAT_OOB_FILL_NONE);
    }
    {
        cuuint64_t gd[2] = {896, 2048}; cuuint64_t gs[1] = {1792}; cuuint32_t bx[2] = {112, 64}; cuuint32_t es[2] = {1, 1};
        enc(&mout, CU_TENSOR_MAP_DATA_TYPE_BFLOAT16, 2, d_out, gd, gs, bx, es, CU_TENSOR_MAP_INTERLEAVE_NONE, CU_TENSOR_MAP_SWIZZLE_NONE, CU_TENSOR_MAP_L2_PROMOTION_NONE, CU_TENSOR_MAP_FLOAT_OOB_FILL_NONE);
    }
    {
        cuuint64_t gd[3] = {1024, 2, 448}; cuuint64_t gs[2] = {2048, 4096}; cuuint32_t bx[3] = {64, 2, 56}; cuuint32_t es[3] = {1, 1, 1};
        enc(&mut, CU_TENSOR_MAP_DATA_TYPE_BFLOAT16, 3, ut_ptr, gd, gs, bx, es, CU_TENSOR_MAP_INTERLEAVE_NONE, CU_TENSOR_MAP_SWIZZLE_NONE, CU_TENSOR_MAP_L2_PROMOTION_NONE, CU_TENSOR_MAP_FLOAT_OOB_FILL_NONE);
    }
    Params p;
    p.wk = (const bf16*)d_in[2]; p.wv = (const bf16*)d_in[3];
    p.lar = (const bf16*)d_in[6]; p.aim = (const bf16*)d_in[7]; p.cre = (const bf16*)d_in[8]; p.cim = (const bf16*)d_in[9];
    p.ldt = (const bf16*)d_in[10]; p.dsk = (const bf16*)d_in[11];
    k_fused<<<132, 640, SM_TOTAL>>>(mx, mwq, mwo, mu, myt, mout, mut, p);
}
```
